```python
import torch

def _softmax(x, axis=-1):
    return torch.softmax(x, dim=axis)

def _gelu(x):
    return torch.nn.functional.gelu(x, approximate='tanh')

def _silu(x):
    return torch.nn.functional.silu(x)

def _sigmoid(x):
    return torch.sigmoid(x)

def _layernorm(x, axis=-1, eps=1e-05):
    m = x.mean(dim=axis, keepdim=True)
    v = x.var(dim=axis, keepdim=True, unbiased=False)
    return (x - m) / torch.sqrt(v + eps)

def _scatter_add(tgt, idx, src, axis=0):
    return tgt.clone().index_add_(axis, idx, src)

def _segment_sum(src, seg, n):
    out = torch.zeros((n,) + src.shape[1:], dtype=src.dtype)
    return out.index_add_(0, seg, src)

def _pad(x, pw):
    flat = tuple((v for pair in reversed(pw) for v in pair))
    return torch.nn.functional.pad(x, flat)
kernel_name = 'adaLN_cond__memory_aug_recurrent_mem_tr__mixer_s_mlp__prompt'

def setup_inputs():

    _w = lambda a: (lambda t: t.to(torch.bfloat16) if t.is_floating_point() else t)(torch.as_tensor(a))

    def _A_setup():
        B, S, Dm = (1, 2048, 512)
        H, Dh = (32, 128)
        M, seg = (8, 32)
        seg = min(seg, S)
        S = S // seg * seg
        return {'x': _w((lambda *s: torch.randn(*s, dtype=torch.bfloat16) * 0.05)(B, S, Dm)), 'mem0': _w((lambda *s: torch.randn(*s, dtype=torch.bfloat16) * 0.4)(B, M, Dm)), 'Wq': _w((lambda *s: torch.randn(*s, dtype=torch.bfloat16) * 3.2)(Dm, H, Dh) * Dm ** (-0.5)), 'Wk': _w((lambda *s: torch.randn(*s, dtype=torch.bfloat16) * 3.2)(Dm, H, Dh) * Dm ** (-0.5)), 'Wv': _w((lambda *s: torch.randn(*s, dtype=torch.bfloat16) * 0.4)(Dm, H, Dh) * Dm ** (-0.5)), 'Wo': _w((lambda *s: torch.randn(*s, dtype=torch.bfloat16) * 0.4)(H, Dh, Dm) * (H * Dh) ** (-0.5)), 'seg_len': seg}
    _A_in = _A_setup()

    def _B_setup():
        B, S, D, F = (1, 2048, 512, 1376)
        return {'x': _w((lambda *s: torch.randn(*s, dtype=torch.bfloat16) * 0.05)(B, S, D)), 'w1': _w((lambda *s: torch.randn(*s, dtype=torch.bfloat16) * 3.2)(D, D) * D ** (-0.5)), 'w2': _w((lambda *s: torch.randn(*s, dtype=torch.bfloat16) * 3.2)(D, D) * D ** (-0.5)), 'w3': _w((lambda *s: torch.randn(*s, dtype=torch.bfloat16) * 3.2)(D, F) * D ** (-0.5)), 'w4': _w((lambda *s: torch.randn(*s, dtype=torch.bfloat16) * 3.2)(F, D) * F ** (-0.5))}
    _B_in = _B_setup()
    return {'A_x': _A_in['x'], 'A_mem0': _A_in['mem0'], 'A_Wq': _A_in['Wq'], 'A_Wk': _A_in['Wk'], 'A_Wv': _A_in['Wv'], 'A_Wo': _A_in['Wo'], 'A_seg_len': _A_in['seg_len'], 'B_x': _B_in['x'], 'B_w1': _B_in['w1'], 'B_w2': _B_in['w2'], 'B_w3': _B_in['w3'], 'B_w4': _B_in['w4'], 'c': _w((lambda *s: torch.randn(*s, dtype=torch.bfloat16) * 0.1)(1, 512) * 8.0), 'w_mod': _w((lambda *s: torch.randn(*s, dtype=torch.bfloat16) * 0.1)(512, 6 * 512) * 512 ** (-0.5) * 8.0)}

def reference(A_x, A_mem0, A_Wq, A_Wk, A_Wv, A_Wo, A_seg_len, B_x, B_w1, B_w2, B_w3, B_w4, c, w_mod):

    def _A_ref(x, mem0, Wq, Wk, Wv, Wo, seg_len):
        B, S, Dm = x.shape
        H, Dh = (Wq.shape[1], Wq.shape[2])
        M = mem0.shape[1]
        scale = Dh ** (-0.5)
        n_seg = S // seg_len
        L = M + seg_len
        idx = torch.arange(L)
        mask = (idx[:, None] < M) | (idx[:, None] >= idx[None, :])
        mem = mem0
        outs = []
        for s in range(n_seg):
            xs = x[:, s * seg_len:(s + 1) * seg_len, :].clone()
            h = torch.concatenate([mem, xs], axis=1)
            q = torch.einsum('btd,dhe->bhte', h, Wq)
            k = torch.einsum('btd,dhe->bhte', h, Wk)
            v = torch.einsum('btd,dhe->bhte', h, Wv)
            scores = torch.einsum('bhqe,bhke->bhqk', q, k) * scale
            scores = torch.where(mask[None, None], scores, -1000000000.0)
            p = _softmax(scores, axis=-1)
            o = torch.einsum('bhqk,bhke->bhqe', p, v)
            o = torch.einsum('bhte,hed->btd', o, Wo)
            mem = o[:, :M, :].clone()
            outs.append(o[:, M:, :])
        return torch.concatenate(outs, axis=1)

    def _B_ref(x, w1, w2, w3, w4):
        B, S, D = x.shape
        h = _gelu(_layernorm(x, axis=-1) @ w1)
        c = D // 4
        g0 = _pad(h[:, :, 0 * c:1 * c], ((0, 0), (1, 0), (0, 0)))[:, :S, :]
        g1 = _pad(h[:, :, 1 * c:2 * c], ((0, 0), (0, 1), (0, 0)))[:, 1:, :]
        g2 = _pad(h[:, :, 2 * c:3 * c], ((0, 0), (2, 0), (0, 0)))[:, :S, :]
        g3 = _pad(h[:, :, 3 * c:], ((0, 0), (0, 2), (0, 0)))[:, 2:, :]
        hs = torch.concatenate([g0, g1, g2, g3], axis=-1) @ w2
        x1 = x + hs
        h2 = _gelu(_layernorm(x1, axis=-1) @ w3) @ w4
        return x1 + h2
    x = A_x
    mod = (_silu(c) @ w_mod).reshape(c.shape[0], 6, 1, -1)
    sa, ca, ga, sb, cb, gb = (mod[:, 0].clone(), mod[:, 1].clone(), mod[:, 2].clone(), mod[:, 3].clone(), mod[:, 4].clone(), mod[:, 5].clone())
    h = _layernorm(x, axis=-1) * (1 + ca) + sa
    x = x + ga * _A_ref(h, A_mem0, A_Wq, A_Wk, A_Wv, A_Wo, A_seg_len)
    h = _layernorm(x, axis=-1) * (1 + cb) + sb
    x = x + gb * _B_ref(h, B_w1, B_w2, B_w3, B_w4)
    return x
```

```cpp
#include <cuda_runtime.h>
#include <cuda_bf16.h>
#include <stdint.h>
#include <cuda.h>

typedef __nv_bfloat16 bf16;
typedef unsigned long long u64;

constexpr int S_ = 2048;
constexpr int D_ = 512;
constexpr int H_ = 32;
constexpr int DH_ = 128;
constexpr int HD_ = 4096;
constexpr int MEM_ = 8;
constexpr int SEG_ = 32;
constexpr int NSEG_ = 64;
constexpr int F_ = 1376;

__device__ float g_mod[6 * D_];
__device__ unsigned int g_epoch;
__device__ bf16 g_h[S_ * D_];
__device__ bf16 g_qkv[(size_t)S_ * 3 * HD_];
__device__ bf16 g_km[NSEG_ * MEM_ * HD_];
__device__ bf16 g_vm[NSEG_ * MEM_ * HD_];
__device__ bf16 g_ox[(size_t)S_ * HD_];
__device__ bf16 g_x1[S_ * D_];
__device__ bf16 g_hb[S_ * D_];
__device__ bf16 g_hn[S_ * D_];
__device__ bf16 g_g1[S_ * D_];
__device__ bf16 g_x1b[S_ * D_];
__device__ bf16 g_hn2[S_ * D_];
__device__ bf16 g_g2[S_ * F_];
__device__ float g_part[2 * S_ * D_];
__device__ u64 g_e1[128 * 384];
__device__ u64 g_p1[128 * 32 * 32];
__device__ u64 g_p2[2048];
__device__ unsigned int g_err;
#define TSTAMP(i)

__device__ __forceinline__ float bf2f(bf16 x) { return __bfloat162float(x); }
__device__ __forceinline__ bf16 f2bf(float x) { return __float2bfloat16_rn(x); }
__device__ __forceinline__ float rbf(float x) { return __bfloat162float(__float2bfloat16_rn(x)); }
__device__ __forceinline__ uint32_t pack_bf2(float lo, float hi) {
    bf16 a = f2bf(lo), b = f2bf(hi);
    return (uint32_t)__bfloat16_as_ushort(a) | ((uint32_t)__bfloat16_as_ushort(b) << 16);
}
__device__ __forceinline__ float lo_bf(uint32_t v) { return __uint_as_float(v << 16); }
__device__ __forceinline__ float hi_bf(uint32_t v) { return __uint_as_float(v & 0xffff0000u); }

__device__ __forceinline__ uint32_t smem_u32(const void* p) { return (uint32_t)__cvta_generic_to_shared(p); }

__device__ __forceinline__ void ldmatrix_x4(uint32_t& r0, uint32_t& r1, uint32_t& r2, uint32_t& r3, uint32_t addr) {
    asm volatile("ldmatrix.sync.aligned.m8n8.x4.shared.b16 {%0,%1,%2,%3}, [%4];"
                 : "=r"(r0), "=r"(r1), "=r"(r2), "=r"(r3) : "r"(addr));
}
__device__ __forceinline__ void ldmatrix_x4_trans(uint32_t& r0, uint32_t& r1, uint32_t& r2, uint32_t& r3, uint32_t addr) {
    asm volatile("ldmatrix.sync.aligned.m8n8.x4.trans.shared.b16 {%0,%1,%2,%3}, [%4];"
                 : "=r"(r0), "=r"(r1), "=r"(r2), "=r"(r3) : "r"(addr));
}
__device__ __forceinline__ void mma_bf16(float (&d)[4], const uint32_t (&a)[4], uint32_t b0, uint32_t b1) {
    asm volatile("mma.sync.aligned.m16n8k16.row.col.f32.bf16.bf16.f32 {%0,%1,%2,%3}, {%4,%5,%6,%7}, {%8,%9}, {%0,%1,%2,%3};"
                 : "+f"(d[0]), "+f"(d[1]), "+f"(d[2]), "+f"(d[3])
                 : "r"(a[0]), "r"(a[1]), "r"(a[2]), "r"(a[3]), "r"(b0), "r"(b1));
}
__device__ __forceinline__ void cp_async16(uint32_t dst, const void* src, bool valid) {
    int sz = valid ? 16 : 0;
    asm volatile("cp.async.cg.shared.global [%0], [%1], 16, %2;" :: "r"(dst), "l"(src), "r"(sz));
}
__device__ __forceinline__ void cp_async_commit() { asm volatile("cp.async.commit_group;"); }
template <int N> __device__ __forceinline__ void cp_async_wait() { asm volatile("cp.async.wait_group %0;" :: "n"(N)); }

__device__ __forceinline__ u64 ld_relaxed_u64(const u64* p) {
    u64 v; asm volatile("ld.relaxed.gpu.global.u64 %0, [%1];" : "=l"(v) : "l"(p) : "memory"); return v;
}
__device__ __forceinline__ void st_relaxed_u64(u64* p, u64 v) {
    asm volatile("st.relaxed.gpu.global.u64 [%0], %1;" :: "l"(p), "l"(v) : "memory");
}

__device__ __forceinline__ float gelu_tanh(float x) {
    const float k0 = 0.7978845608028654f, k1 = 0.044715f;
    float inner = k0 * (x + k1 * x * x * x);
    return 0.5f * x * (1.0f + tanhf(inner));
}

__global__ void __launch_bounds__(256) mod_kernel(const bf16* __restrict__ c, const bf16* __restrict__ w_mod) {
    __shared__ float sc[D_];
    __shared__ float part[4][64];
    int tid = threadIdx.x;
    for (int i = tid; i < D_; i += 256) {
        float x = bf2f(c[i]);
        sc[i] = rbf(x / (1.0f + __expf(-x)));
    }
    __syncthreads();
    int col = blockIdx.x * 64 + (tid & 63);
    int kg = tid >> 6;
    float acc = 0.f;
    for (int k = kg * 128; k < kg * 128 + 128; k++) {
        acc += sc[k] * bf2f(w_mod[(size_t)k * 3072 + col]);
    }
    part[kg][tid & 63] = acc;
    __syncthreads();
    if (tid < 64) {
        float s = part[0][tid] + part[1][tid] + part[2][tid] + part[3][tid];
        g_mod[blockIdx.x * 64 + tid] = rbf(s);
    }
    if (blockIdx.x == 0 && tid == 0) g_epoch = g_epoch + 1;
}

__device__ __forceinline__ float warp_sum(float v) {
    #pragma unroll
    for (int o = 16; o > 0; o >>= 1) v += __shfl_xor_sync(0xffffffffu, v, o);
    return v;
}

__device__ __forceinline__ void ln_row_bf16(float (&v)[16]) {
    float s = 0.f;
    #pragma unroll
    for (int i = 0; i < 16; i++) s += v[i];
    s = warp_sum(s);
    float mean = s * (1.0f / 512.0f);
    float q = 0.f;
    #pragma unroll
    for (int i = 0; i < 16; i++) { float d = v[i] - mean; q += d * d; }
    q = warp_sum(q);
    float var = q * (1.0f / 512.0f);
    float mean_b = rbf(mean);
    float var_b = rbf(var);
    float den = rbf(sqrtf(rbf(var_b + 1e-5f)));
    #pragma unroll
    for (int i = 0; i < 16; i++) {
        float d = rbf(v[i] - mean_b);
        v[i] = rbf(d / den);
    }
}

__device__ __forceinline__ void load_row16(const bf16* __restrict__ p, int lane, float (&v)[16]) {
    #pragma unroll
    for (int hh = 0; hh < 2; hh++) {
        uint4 u = *reinterpret_cast<const uint4*>(p + hh * 256 + lane * 8);
        uint32_t w[4] = {u.x, u.y, u.z, u.w};
        #pragma unroll
        for (int e = 0; e < 4; e++) { v[hh * 8 + 2 * e] = lo_bf(w[e]); v[hh * 8 + 2 * e + 1] = hi_bf(w[e]); }
    }
}
__device__ __forceinline__ void store_row16(bf16* __restrict__ p, int lane, const float (&v)[16]) {
    #pragma unroll
    for (int hh = 0; hh < 2; hh++) {
        uint4 u;
        u.x = pack_bf2(v[hh * 8 + 0], v[hh * 8 + 1]);
        u.y = pack_bf2(v[hh * 8 + 2], v[hh * 8 + 3]);
        u.z = pack_bf2(v[hh * 8 + 4], v[hh * 8 + 5]);
        u.w = pack_bf2(v[hh * 8 + 6], v[hh * 8 + 7]);
        *reinterpret_cast<uint4*>(p + hh * 256 + lane * 8) = u;
    }
}
__device__ __forceinline__ int col_of(int i, int lane) { return (i >> 3) * 256 + lane * 8 + (i & 7); }

__global__ void __launch_bounds__(256) ln_mod_kernel(const bf16* __restrict__ x, bf16* __restrict__ out, int shift_off, int scale_off) {
    int warp = threadIdx.x >> 5, lane = threadIdx.x & 31;
    int row = blockIdx.x * 8 + warp;
    float v[16];
    load_row16(x + (size_t)row * D_, lane, v);
    ln_row_bf16(v);
    #pragma unroll
    for (int i = 0; i < 16; i++) {
        int cidx = col_of(i, lane);
        float sc = rbf(1.0f + g_mod[scale_off + cidx]);
        float t = rbf(v[i] * sc);
        v[i] = rbf(t + g_mod[shift_off + cidx]);
    }
    store_row16(out + (size_t)row * D_, lane, v);
}

__global__ void __launch_bounds__(256) res_ln2_kernel(const bf16* __restrict__ x) {
    int warp = threadIdx.x >> 5, lane = threadIdx.x & 31;
    int row = blockIdx.x * 8 + warp;
    float v[16], a[16];
    load_row16(x + (size_t)row * D_, lane, v);
    #pragma unroll
    for (int i = 0; i < 16; i++) { size_t o = (size_t)row * D_ + col_of(i, lane); a[i] = rbf(g_part[o] + g_part[(size_t)S_ * D_ + o]); }
    #pragma unroll
    for (int i = 0; i < 16; i++) {
        int cidx = col_of(i, lane);
        float t = rbf(g_mod[2 * D_ + cidx] * a[i]);
        v[i] = rbf(v[i] + t);
    }
    store_row16(g_x1 + (size_t)row * D_, lane, v);
    ln_row_bf16(v);
    #pragma unroll
    for (int i = 0; i < 16; i++) {
        int cidx = col_of(i, lane);
        float sc = rbf(1.0f + g_mod[4 * D_ + cidx]);
        float t = rbf(v[i] * sc);
        v[i] = rbf(t + g_mod[3 * D_ + cidx]);
    }
    store_row16(g_hb + (size_t)row * D_, lane, v);
    ln_row_bf16(v);
    store_row16(g_hn + (size_t)row * D_, lane, v);
}

__global__ void __launch_bounds__(256) ln_kernel(const bf16* __restrict__ in, bf16* __restrict__ out) {
    int warp = threadIdx.x >> 5, lane = threadIdx.x & 31;
    int row = blockIdx.x * 8 + warp;
    float v[16];
    load_row16(in + (size_t)row * D_, lane, v);
    ln_row_bf16(v);
    store_row16(out + (size_t)row * D_, lane, v);
}

constexpr int GBM = 128, GBN = 128, GBK = 32;
constexpr int GAS = GBK + 8;
constexpr int GBS = GBN + 8;

struct GemmParams {
    const bf16* A; int lda;
    const bf16* B0; const bf16* B1; const bf16* B2; int ldb; int nsplit;
    int M, N, K;
    bf16* out; int ldc;
    const bf16* res; const bf16* res2;
    int shifted;
};

template <int EPI>
__global__ void __launch_bounds__(256) gemm_kernel(GemmParams p) {
    extern __shared__ __align__(16) unsigned char smraw[];
    bf16* As = reinterpret_cast<bf16*>(smraw);
    bf16* Bs = As + 3 * GBM * GAS;
    const int tid = threadIdx.x, warp = tid >> 5, lane = tid & 31;
    const int wm = warp >> 2, wn = warp & 3;
    const int m0 = blockIdx.y * GBM, n0 = blockIdx.x * GBN;
    const bf16* Bp; int nb;
    {
        int sel = n0 / p.nsplit;
        Bp = sel == 0 ? p.B0 : (sel == 1 ? p.B1 : p.B2);
        nb = n0 - sel * p.nsplit;
    }
    const int ktiles = (p.K + GBK - 1) / GBK;

    auto load_stage = [&](int st, int kt) {
        int k0 = kt * GBK;
        #pragma unroll
        for (int i = 0; i < 2; i++) {
            int ch = tid + i * 256;
            int r = ch >> 2, cc = (ch & 3) * 8;
            int grow = m0 + r;
            int gk = k0 + cc;
            if (p.shifted) {
                int grp = gk >> 7;
                int sh = (grp == 0) ? -1 : (grp == 1) ? 1 : (grp == 2) ? -2 : 2;
                grow += sh;
            }
            bool ok = (grow >= 0) && (grow < p.M) && (gk < p.K);
            const bf16* src = p.A + (size_t)(ok ? grow : 0) * p.lda + (ok ? gk : 0);
            cp_async16(smem_u32(As + (st * GBM + r) * GAS + cc), src, ok);
        }
        #pragma unroll
        for (int i = 0; i < 2; i++) {
            int ch = tid + i * 256;
            int r = ch >> 4, cc = (ch & 15) * 8;
            int gk = k0 + r;
            int gn = nb + cc;
            bool ok = (gk < p.K) && (n0 + cc < p.N);
            const bf16* src = Bp + (size_t)(ok ? gk : 0) * p.ldb + (ok ? gn : 0);
            cp_async16(smem_u32(Bs + (st * GBK + r) * GBS + cc), src, ok);
        }
    };

    float acc[4][4][4];
    #pragma unroll
    for (int i = 0; i < 4; i++)
        #pragma unroll
        for (int j = 0; j < 4; j++)
            #pragma unroll
            for (int e = 0; e < 4; e++) acc[i][j][e] = 0.f;

    load_stage(0, 0); cp_async_commit();
    if (ktiles > 1) load_stage(1, 1);
    cp_async_commit();

    for (int kt = 0; kt < ktiles; kt++) {
        cp_async_wait<1>();
        __syncthreads();
        if (kt + 2 < ktiles) load_stage((kt + 2) % 3, kt + 2);
        cp_async_commit();
        int st = kt % 3;
        const bf16* Ab = As + st * GBM * GAS;
        const bf16* Bb = Bs + st * GBK * GBS;
        #pragma unroll
        for (int ks = 0; ks < 2; ks++) {
            uint32_t af[4][4];
            #pragma unroll
            for (int i = 0; i < 4; i++) {
                int r = wm * 64 + i * 16 + (lane & 15);
                int cc = ks * 16 + (lane >> 4) * 8;
                ldmatrix_x4(af[i][0], af[i][1], af[i][2], af[i][3], smem_u32(Ab + r * GAS + cc));
            }
            uint32_t bfr[4][2];
            #pragma unroll
            for (int j2 = 0; j2 < 2; j2++) {
                int kr = ks * 16 + (lane & 7) + ((lane >> 3) & 1) * 8;
                int nc = wn * 32 + j2 * 16 + (lane >> 4) * 8;
                uint32_t r0, r1, r2, r3;
                ldmatrix_x4_trans(r0, r1, r2, r3, smem_u32(Bb + kr * GBS + nc));
                bfr[j2 * 2][0] = r0; bfr[j2 * 2][1] = r1;
                bfr[j2 * 2 + 1][0] = r2; bfr[j2 * 2 + 1][1] = r3;
            }
            #pragma unroll
            for (int i = 0; i < 4; i++)
                #pragma unroll
                for (int j = 0; j < 4; j++)
                    mma_bf16(acc[i][j], af[i], bfr[j][0], bfr[j][1]);
        }
    }

    const int g = lane >> 2, t = lane & 3;
    #pragma unroll
    for (int i = 0; i < 4; i++) {
        #pragma unroll
        for (int j = 0; j < 4; j++) {
            #pragma unroll
            for (int hh = 0; hh < 2; hh++) {
                int row = m0 + wm * 64 + i * 16 + g + hh * 8;
                int col = n0 + wn * 32 + j * 8 + 2 * t;
                if (row >= p.M || col >= p.N) continue;
                float c0 = acc[i][j][hh * 2], c1 = acc[i][j][hh * 2 + 1];
                size_t off = (size_t)row * p.ldc + col;
                if (EPI == 0) {
                    *reinterpret_cast<uint32_t*>(p.out + off) = pack_bf2(c0, c1);
                } else if (EPI == 1) {
                    *reinterpret_cast<uint32_t*>(p.out + off) = pack_bf2(gelu_tanh(rbf(c0)), gelu_tanh(rbf(c1)));
                } else if (EPI == 2) {
                    uint32_t rr = *reinterpret_cast<const uint32_t*>(p.res + off);
                    *reinterpret_cast<uint32_t*>(p.out + off) = pack_bf2(lo_bf(rr) + rbf(c0), hi_bf(rr) + rbf(c1));
                } else {
                    uint32_t r1 = *reinterpret_cast<const uint32_t*>(p.res + off);
                    uint32_t r2 = *reinterpret_cast<const uint32_t*>(p.res2 + off);
                    float b0 = rbf(lo_bf(r1) + rbf(c0)), b1 = rbf(hi_bf(r1) + rbf(c1));
                    float gb0 = g_mod[5 * D_ + col], gb1 = g_mod[5 * D_ + col + 1];
                    float o0 = lo_bf(r2) + rbf(gb0 * b0), o1 = hi_bf(r2) + rbf(gb1 * b1);
                    *reinterpret_cast<uint32_t*>(p.out + off) = pack_bf2(o0, o1);
                }
            }
        }
    }
}

struct WgParams {
    int M, N, K, ldc, nsplit, shifted, ksplit_len;
    bf16* out; float* outf;
    const bf16* res; const bf16* res2;
};
__device__ __forceinline__ void mbar_init_(uint32_t m, uint32_t c) { asm volatile("mbarrier.init.shared::cta.b64 [%0], %1;" :: "r"(m), "r"(c)); }
__device__ __forceinline__ void mbar_expect_(uint32_t m, uint32_t b) { asm volatile("mbarrier.arrive.expect_tx.shared::cta.b64 _, [%0], %1;" :: "r"(m), "r"(b) : "memory"); }
__device__ __forceinline__ void mbar_arrive_(uint32_t m) { asm volatile("mbarrier.arrive.shared::cta.b64 _, [%0];" :: "r"(m) : "memory"); }
__device__ __forceinline__ void mbar_wait_(uint32_t m, uint32_t par) {
    asm volatile("{ .reg .pred p; WL: mbarrier.try_wait.parity.shared::cta.b64 p, [%0], %1; @p bra WD; bra WL; WD: }" :: "r"(m), "r"(par) : "memory");
}
__device__ __forceinline__ void tma2d(uint32_t dst, const CUtensorMap* map, int c0, int c1, uint32_t mbar) {
    asm volatile("cp.async.bulk.tensor.2d.shared::cluster.global.mbarrier::complete_tx::bytes [%0], [%1, {%3, %4}], [%2];"
                 :: "r"(dst), "l"(map), "r"(mbar), "r"(c0), "r"(c1) : "memory");
}
__device__ __forceinline__ u64 mkdesc(uint32_t addr, uint32_t lbo, uint32_t sbo) {
    return (u64)((addr & 0x3FFFF) >> 4) | ((u64)((lbo >> 4) & 0x3FFF) << 16) | ((u64)((sbo >> 4) & 0x3FFF) << 32) | (1ull << 62);
}
__device__ __forceinline__ void wgmma128(float (&d)[64], u64 da, u64 db) {
    asm volatile("{ wgmma.mma_async.sync.aligned.m64n128k16.f32.bf16.bf16 "
        "{%0,%1,%2,%3,%4,%5,%6,%7,%8,%9,%10,%11,%12,%13,%14,%15,%16,%17,%18,%19,%20,%21,%22,%23,%24,%25,%26,%27,%28,%29,%30,%31,"
        "%32,%33,%34,%35,%36,%37,%38,%39,%40,%41,%42,%43,%44,%45,%46,%47,%48,%49,%50,%51,%52,%53,%54,%55,%56,%57,%58,%59,%60,%61,%62,%63},"
        " %64, %65, 1, 1, 1, 0, 1; }"
        : "+f"(d[0]),"+f"(d[1]),"+f"(d[2]),"+f"(d[3]),"+f"(d[4]),"+f"(d[5]),"+f"(d[6]),"+f"(d[7]),"+f"(d[8]),"+f"(d[9]),"+f"(d[10]),"+f"(d[11]),"+f"(d[12]),"+f"(d[13]),"+f"(d[14]),"+f"(d[15]),
          "+f"(d[16]),"+f"(d[17]),"+f"(d[18]),"+f"(d[19]),"+f"(d[20]),"+f"(d[21]),"+f"(d[22]),"+f"(d[23]),"+f"(d[24]),"+f"(d[25]),"+f"(d[26]),"+f"(d[27]),"+f"(d[28]),"+f"(d[29]),"+f"(d[30]),"+f"(d[31]),
          "+f"(d[32]),"+f"(d[33]),"+f"(d[34]),"+f"(d[35]),"+f"(d[36]),"+f"(d[37]),"+f"(d[38]),"+f"(d[39]),"+f"(d[40]),"+f"(d[41]),"+f"(d[42]),"+f"(d[43]),"+f"(d[44]),"+f"(d[45]),"+f"(d[46]),"+f"(d[47]),
          "+f"(d[48]),"+f"(d[49]),"+f"(d[50]),"+f"(d[51]),"+f"(d[52]),"+f"(d[53]),"+f"(d[54]),"+f"(d[55]),"+f"(d[56]),"+f"(d[57]),"+f"(d[58]),"+f"(d[59]),"+f"(d[60]),"+f"(d[61]),"+f"(d[62]),"+f"(d[63])
        : "l"(da), "l"(db));
}
constexpr int WST = 4;
constexpr int WG_SMEM = WST * 32768 + 1024 + 256;

template <int EPI>
__global__ void __launch_bounds__(288) wg_gemm(const __grid_constant__ CUtensorMap mA, const __grid_constant__ CUtensorMap mB0,
                                               const __grid_constant__ CUtensorMap mB1, const __grid_constant__ CUtensorMap mB2, WgParams p) {
    extern __shared__ unsigned char wsm_raw[];
    uint32_t base = (smem_u32(wsm_raw) + 1023) & ~1023u;
    uint32_t bars = base + WST * 32768;
    const int tid = threadIdx.x, warp = tid >> 5, lane = tid & 31;
    const int m0 = blockIdx.y * 128, n0 = blockIdx.x * 128;
    const int kbeg = blockIdx.z * p.ksplit_len;
    const int kend = min(p.K, kbeg + p.ksplit_len);
    const int ktiles = (kend - kbeg + 63) / 64;
    if (tid == 0) {
        for (int i = 0; i < WST; i++) { mbar_init_(bars + i * 8, 1); mbar_init_(bars + 64 + i * 8, 2); }
        asm volatile("fence.mbarrier_init.release.cluster;" ::: "memory");
    }
    __syncthreads();
    if (warp == 8) {
        if (lane == 0) {
            int sel = n0 / p.nsplit;
            const CUtensorMap* mb = sel == 0 ? &mB0 : (sel == 1 ? &mB1 : &mB2);
            int nb = n0 - sel * p.nsplit;
            for (int kt = 0; kt < ktiles; kt++) {
                int st = kt % WST;
                if (kt >= WST) mbar_wait_(bars + 64 + st * 8, ((kt / WST) - 1) & 1);
                mbar_expect_(bars + st * 8, 32768);
                int k0 = kbeg + kt * 64;
                int row = m0;
                if (p.shifted) { int grp = k0 >> 7; row += (grp == 0) ? -1 : (grp == 1) ? 1 : (grp == 2) ? -2 : 2; }
                uint32_t sa = base + st * 32768, sb = sa + 16384;
                tma2d(sa, &mA, k0, row, bars + st * 8);
                tma2d(sb, mb, nb, k0, bars + st * 8);
                tma2d(sb + 8192, mb, nb + 64, k0, bars + st * 8);
            }
        }
        return;
    }
    const int wgi = warp >> 2;
    float acc[64];
    #pragma unroll
    for (int i = 0; i < 64; i++) acc[i] = 0.f;
    for (int kt = 0; kt < ktiles; kt++) {
        int st = kt % WST;
        mbar_wait_(bars + st * 8, (kt / WST) & 1);
        uint32_t sa = base + st * 32768 + wgi * 8192, sb = base + st * 32768 + 16384;
        asm volatile("wgmma.fence.sync.aligned;" ::: "memory");
        #pragma unroll
        for (int ks = 0; ks < 4; ks++) wgmma128(acc, mkdesc(sa + ks * 32, 16, 1024), mkdesc(sb + ks * 2048, 8192, 1024));
        asm volatile("wgmma.commit_group.sync.aligned;" ::: "memory");
        asm volatile("wgmma.wait_group.sync.aligned 0;" ::: "memory");
        if ((tid & 127) == 0) mbar_arrive_(bars + 64 + st * 8);
    }
    const int g = lane >> 2, t = lane & 3;
    #pragma unroll
    for (int i = 0; i < 16; i++) {
        #pragma unroll
        for (int hh = 0; hh < 2; hh++) {
            int row = m0 + wgi * 64 + (warp & 3) * 16 + g + hh * 8;
            int col = n0 + i * 8 + 2 * t;
            if (col >= p.N) continue;
            float c0 = acc[4 * i + 2 * hh], c1 = acc[4 * i + 2 * hh + 1];
            size_t off = (size_t)row * p.ldc + col;
            if (EPI == 0) {
                *reinterpret_cast<uint32_t*>(p.out + off) = pack_bf2(c0, c1);
            } else if (EPI == 1) {
                *reinterpret_cast<uint32_t*>(p.out + off) = pack_bf2(gelu_tanh(rbf(c0)), gelu_tanh(rbf(c1)));
            } else if (EPI == 2) {
                uint32_t rr = *reinterpret_cast<const uint32_t*>(p.res + off);
                *reinterpret_cast<uint32_t*>(p.out + off) = pack_bf2(lo_bf(rr) + rbf(c0), hi_bf(rr) + rbf(c1));
            } else if (EPI == 3) {
                uint32_t r1 = *reinterpret_cast<const uint32_t*>(p.res + off);
                uint32_t r2 = *reinterpret_cast<const uint32_t*>(p.res2 + off);
                float b0 = rbf(lo_bf(r1) + rbf(c0)), b1 = rbf(hi_bf(r1) + rbf(c1));
                float o0 = lo_bf(r2) + rbf(g_mod[5 * D_ + col] * b0), o1 = hi_bf(r2) + rbf(g_mod[5 * D_ + col + 1] * b1);
                *reinterpret_cast<uint32_t*>(p.out + off) = pack_bf2(o0, o1);
            } else {
                *reinterpret_cast<float2*>(p.outf + (size_t)blockIdx.z * p.M * p.ldc + off) = make_float2(c0, c1);
            }
        }
    }
}

typedef CUresult (*EncFn)(CUtensorMap*, CUtensorMapDataType, cuuint32_t, void*, const cuuint64_t*, const cuuint64_t*,
                          const cuuint32_t*, const cuuint32_t*, CUtensorMapInterleave, CUtensorMapSwizzle,
                          CUtensorMapL2promotion, CUtensorMapFloatOOBfill);
static CUtensorMap make_map(EncFn enc, const void* ptr, int inner, int outer, int box0, int box1) {
    CUtensorMap m;
    cuuint64_t dims[2] = {(cuuint64_t)inner, (cuuint64_t)outer};
    cuuint64_t strides[1] = {(cuuint64_t)inner * 2};
    cuuint32_t box[2] = {(cuuint32_t)box0, (cuuint32_t)box1};
    cuuint32_t es[2] = {1, 1};
    enc(&m, CU_TENSOR_MAP_DATA_TYPE_BFLOAT16, 2, (void*)ptr, dims, strides, box, es, CU_TENSOR_MAP_INTERLEAVE_NONE,
        CU_TENSOR_MAP_SWIZZLE_128B, CU_TENSOR_MAP_L2_PROMOTION_L2_256B, CU_TENSOR_MAP_FLOAT_OOB_FILL_NONE);
    return m;
}

constexpr int RS = 136;
#define SLP 100
constexpr int POLL_LIMIT = 1 << 18;

__global__ void __launch_bounds__(512, 1) recur_kernel(const bf16* __restrict__ mem0,
                                                       const bf16* __restrict__ Wq, const bf16* __restrict__ Wk,
                                                       const bf16* __restrict__ Wv, const bf16* __restrict__ Wo) {
    extern __shared__ __align__(16) unsigned char rsm[];
    typedef float red_t[8][100];
    red_t* red = reinterpret_cast<red_t*>(rsm);
    typedef bf16 row_t[RS];
    row_t* Qs = reinterpret_cast<row_t*>(rsm + 25600);
    row_t* Ks = reinterpret_cast<row_t*>(rsm + 25600 + 2176);
    row_t* Vs = reinterpret_cast<row_t*>(rsm + 25600 + 2176 + 13056);
    row_t* Os = reinterpret_cast<row_t*>(rsm + 25600 + 2176 + 26112);
    __shared__ __align__(16) float Ss[8][48];
    __shared__ __align__(16) bf16 Ps[8][56];
    __shared__ __align__(16) float g2x[8][32][4];
    __shared__ float red2[4][32];

    const int tid = threadIdx.x, warp = tid >> 5, lane = tid & 31;
    const int g = lane >> 2, t = lane & 3;
    const int b = blockIdx.x, h = b >> 2, j = b & 3;
    const unsigned int tag0 = g_epoch * 64u;

    const int ks = warp & 7, mg = warp >> 3;
    uint32_t aw[3][4][4];
    #pragma unroll
    for (int i = 0; i < 3; i++) {
        int tile = mg * 3 + i;
        const bf16* W = (tile < 2) ? Wq : (tile < 4 ? Wk : Wv);
        int col0 = h * DH_ + j * 32 + (tile & 1) * 16;
        #pragma unroll
        for (int kk = 0; kk < 4; kk++) {
            int k0 = ks * 64 + kk * 16;
            #pragma unroll
            for (int r = 0; r < 4; r++) {
                int m = g + (r & 1) * 8;
                int k = k0 + 2 * t + (r >> 1) * 8;
                unsigned short lo = __bfloat16_as_ushort(W[(size_t)k * HD_ + col0 + m]);
                unsigned short hi = __bfloat16_as_ushort(W[(size_t)(k + 1) * HD_ + col0 + m]);
                aw[i][kk][r] = (uint32_t)lo | ((uint32_t)hi << 16);
            }
        }
    }
    uint32_t ao[4][4];
    {
        int mt = warp >> 1, kh = warp & 1;
        int col0 = j * 128 + mt * 16;
        #pragma unroll
        for (int kk = 0; kk < 4; kk++) {
            int k0 = h * DH_ + kh * 64 + kk * 16;
            #pragma unroll
            for (int r = 0; r < 4; r++) {
                int m = g + (r & 1) * 8;
                int k = k0 + 2 * t + (r >> 1) * 8;
                unsigned short lo = __bfloat16_as_ushort(Wo[(size_t)k * D_ + col0 + m]);
                unsigned short hi = __bfloat16_as_ushort(Wo[(size_t)(k + 1) * D_ + col0 + m]);
                ao[kk][r] = (uint32_t)lo | ((uint32_t)hi << 16);
            }
        }
    }
    for (int i = tid; i < 8 * RS; i += 512) { Ks[40 + i / RS][i % RS] = f2bf(0.f); Vs[40 + i / RS][i % RS] = f2bf(0.f); }
    for (int i = tid; i < 8 * 56; i += 512) Ps[i / 56][i % 56] = f2bf(0.f);

    auto prefetch_tokens = [&](int s) {
        #pragma unroll
        for (int i = 0; i < 2; i++) {
            int ch = tid + i * 512;
            int which = ch >> 9;
            int r = (ch >> 4) & 31, cc = (ch & 15) * 8;
            const bf16* src = g_qkv + (size_t)(s * SEG_ + r) * (3 * HD_) + (1 + which) * HD_ + h * DH_ + cc;
            bf16* dst = which == 0 ? &Ks[8 + r][cc] : &Vs[8 + r][cc];
            cp_async16(smem_u32(dst), src, true);
        }
        cp_async_commit();
    };
    prefetch_tokens(0);

    for (int s = 0; s < NSEG_; s++) {
        const unsigned int tag = tag0 + s + 1;
        uint32_t bfr[4][2];
        if (s == 0) {
            #pragma unroll
            for (int kk = 0; kk < 4; kk++) {
                int k0 = ks * 64 + kk * 16;
                bfr[kk][0] = *reinterpret_cast<const uint32_t*>(mem0 + g * D_ + k0 + 2 * t);
                bfr[kk][1] = *reinterpret_cast<const uint32_t*>(mem0 + g * D_ + k0 + 2 * t + 8);
            }
        } else {
            const unsigned int ptag = tag - 1;
            int guard = 0;
            bool ok;
            do {
                ok = true;
                #pragma unroll
                for (int kk = 0; kk < 4; kk++) {
                    int kp = (ks * 64 + kk * 16 + 2 * t) >> 1;
                    u64 x0 = ld_relaxed_u64(&g_p2[(kp >> 1) * 16 + g * 2 + (kp & 1)]);
                    u64 x1 = ld_relaxed_u64(&g_p2[((kp + 4) >> 1) * 16 + g * 2 + (kp & 1)]);
                    bfr[kk][0] = (uint32_t)x0; bfr[kk][1] = (uint32_t)x1;
                    ok = ok && ((unsigned)(x0 >> 32) == ptag) && ((unsigned)(x1 >> 32) == ptag);
                }
                if (!ok) __nanosleep(SLP);
                if (++guard > POLL_LIMIT) { g_err = 1; break; }
            } while (!ok);
        }
        TSTAMP(0);
        float d1[3][4];
        #pragma unroll
        for (int i = 0; i < 3; i++) { d1[i][0] = d1[i][1] = d1[i][2] = d1[i][3] = 0.f; }
        #pragma unroll
        for (int kk = 0; kk < 4; kk++)
            #pragma unroll
            for (int i = 0; i < 3; i++) mma_bf16(d1[i], aw[i][kk], bfr[kk][0], bfr[kk][1]);
        #pragma unroll
        for (int i = 0; i < 3; i++) {
            int colb = (mg * 3 + i) * 16;
            red[ks][2 * t][colb + g] = d1[i][0]; red[ks][2 * t + 1][colb + g] = d1[i][1];
            red[ks][2 * t][colb + g + 8] = d1[i][2]; red[ks][2 * t + 1][colb + g + 8] = d1[i][3];
        }
        __syncthreads();
        TSTAMP(1);
        if (tid < 384) {
            int type = tid >> 7, row = (tid >> 4) & 7, pr = tid & 15;
            int c0 = type * 32 + pr * 2;
            float a0 = 0.f, a1 = 0.f;
            #pragma unroll
            for (int q = 0; q < 8; q++) { float2 z = *reinterpret_cast<const float2*>(&red[q][row][c0]); a0 += z.x; a1 += z.y; }
            uint32_t pk = pack_bf2(a0, a1);
            st_relaxed_u64(&g_e1[b * 384 + tid], ((u64)tag << 32) | pk);
        }
        TSTAMP(2);
        if (tid < 384) {
            int type = tid >> 7, row = (tid >> 4) & 7, pr = tid & 15;
            u64 x[4];
            int guard = 0; bool ok;
            do {
                ok = true;
                #pragma unroll
                for (int q = 0; q < 4; q++) x[q] = ld_relaxed_u64(&g_e1[(h * 4 + q) * 384 + tid]);
                #pragma unroll
                for (int q = 0; q < 4; q++) ok = ok && ((unsigned)(x[q] >> 32) == tag);
                if (!ok) __nanosleep(SLP);
                if (++guard > POLL_LIMIT) { g_err = 2; break; }
            } while (!ok);
            #pragma unroll
            for (int q = 0; q < 4; q++) {
                bf16* dst = (type == 0 ? &Qs[row][0] : (type == 1 ? &Ks[row][0] : &Vs[row][0])) + q * 32 + pr * 2;
                *reinterpret_cast<uint32_t*>(dst) = (uint32_t)x[q];
            }
        }
        cp_async_wait<0>();
        __syncthreads();
        TSTAMP(3);
        if (warp < 3) {
            float d[4] = {0.f, 0.f, 0.f, 0.f};
            #pragma unroll
            for (int kk = 0; kk < 8; kk++) {
                uint32_t a[4];
                ldmatrix_x4(a[0], a[1], a[2], a[3], smem_u32(&Ks[warp * 16 + (lane & 15)][kk * 16 + (lane >> 4) * 8]));
                uint32_t b0 = *reinterpret_cast<const uint32_t*>(&Qs[g][kk * 16 + 2 * t]);
                uint32_t b1 = *reinterpret_cast<const uint32_t*>(&Qs[g][kk * 16 + 2 * t + 8]);
                mma_bf16(d, a, b0, b1);
            }
            const float scale = 0.08838834764831845f;
            Ss[2 * t][warp * 16 + g] = rbf(rbf(d[0]) * scale);
            Ss[2 * t + 1][warp * 16 + g] = rbf(rbf(d[1]) * scale);
            Ss[2 * t][warp * 16 + g + 8] = rbf(rbf(d[2]) * scale);
            Ss[2 * t + 1][warp * 16 + g + 8] = rbf(rbf(d[3]) * scale);
        }
        __syncthreads();
        TSTAMP(4);
        if (warp == 0) {
            float v[10];
            float mx = -INFINITY;
            #pragma unroll
            for (int i = 0; i < 10; i++) { v[i] = Ss[g][t + 4 * i]; mx = fmaxf(mx, v[i]); }
            mx = fmaxf(mx, __shfl_xor_sync(0xffffffffu, mx, 1));
            mx = fmaxf(mx, __shfl_xor_sync(0xffffffffu, mx, 2));
            float sum = 0.f;
            #pragma unroll
            for (int i = 0; i < 10; i++) { v[i] = __expf(v[i] - mx); sum += v[i]; }
            sum += __shfl_xor_sync(0xffffffffu, sum, 1);
            sum += __shfl_xor_sync(0xffffffffu, sum, 2);
            float inv = 1.0f / sum;
            #pragma unroll
            for (int i = 0; i < 10; i++) Ps[g][t + 4 * i] = f2bf(v[i] * inv);
        }
        __syncthreads();
        TSTAMP(5);
        if (warp < 8) {
            float d[4] = {0.f, 0.f, 0.f, 0.f};
            #pragma unroll
            for (int kk = 0; kk < 3; kk++) {
                int mi = lane >> 3;
                int krow = kk * 16 + (mi >> 1) * 8 + (lane & 7);
                int dcol = warp * 16 + (mi & 1) * 8;
                uint32_t a[4];
                ldmatrix_x4_trans(a[0], a[1], a[2], a[3], smem_u32(&Vs[krow][dcol]));
                uint32_t b0 = *reinterpret_cast<const uint32_t*>(&Ps[g][kk * 16 + 2 * t]);
                uint32_t b1 = *reinterpret_cast<const uint32_t*>(&Ps[g][kk * 16 + 2 * t + 8]);
                mma_bf16(d, a, b0, b1);
            }
            Os[2 * t][warp * 16 + g] = f2bf(d[0]);
            Os[2 * t + 1][warp * 16 + g] = f2bf(d[1]);
            Os[2 * t][warp * 16 + g + 8] = f2bf(d[2]);
            Os[2 * t + 1][warp * 16 + g + 8] = f2bf(d[3]);
        }
        __syncthreads();
        TSTAMP(6);
        if (j == 0 && tid >= 256 && tid < 512) {
            int q = tid - 256; int which = q >> 7, r = (q >> 4) & 7, cc = (q & 15) * 8;
            bf16* dst = (which == 0 ? g_km : g_vm) + ((size_t)s * MEM_ + r) * HD_ + h * DH_ + cc;
            *reinterpret_cast<uint4*>(dst) = *reinterpret_cast<const uint4*>(which == 0 ? &Ks[r][cc] : &Vs[r][cc]);
        }
        if (s + 1 < NSEG_) prefetch_tokens(s + 1);
        {
            int mt = warp >> 1, kh = warp & 1;
            float d[4] = {0.f, 0.f, 0.f, 0.f};
            #pragma unroll
            for (int kk = 0; kk < 4; kk++) {
                int k0 = kh * 64 + kk * 16;
                uint32_t b0 = *reinterpret_cast<const uint32_t*>(&Os[g][k0 + 2 * t]);
                uint32_t b1 = *reinterpret_cast<const uint32_t*>(&Os[g][k0 + 2 * t + 8]);
                mma_bf16(d, ao[kk], b0, b1);
            }
            if (kh == 1) *reinterpret_cast<float4*>(&g2x[mt][lane][0]) = make_float4(d[0], d[1], d[2], d[3]);
            __syncthreads();
            if (kh == 0) {
                float4 o = *reinterpret_cast<const float4*>(&g2x[mt][lane][0]);
                d[0] += o.x; d[1] += o.y; d[2] += o.z; d[3] += o.w;
                #pragma unroll
                for (int e = 0; e < 4; e++) {
                    int col = mt * 16 + g + (e >> 1) * 8;
                    int row = 2 * t + (e & 1);
                    int r = j * 32 + (col >> 2);
                    int idx = row * 4 + (col & 3);
                    st_relaxed_u64(&g_p1[((size_t)r * 32 + h) * 32 + idx], ((u64)tag << 32) | __float_as_uint(d[e]));
                }
            }
        }
        TSTAMP(7);
        if (warp < 4) {
            u64 x[8];
            int guard = 0; bool ok;
            do {
                ok = true;
                #pragma unroll
                for (int q = 0; q < 8; q++) x[q] = ld_relaxed_u64(&g_p1[((size_t)b * 32 + warp * 8 + q) * 32 + lane]);
                #pragma unroll
                for (int q = 0; q < 8; q++) ok = ok && ((unsigned)(x[q] >> 32) == tag);
                if (!ok) __nanosleep(SLP);
                if (++guard > POLL_LIMIT) { g_err = 3; break; }
            } while (!ok);
            float sacc = 0.f;
            #pragma unroll
            for (int q = 0; q < 8; q++) sacc += __uint_as_float((uint32_t)x[q]);
            red2[warp][lane] = sacc;
            asm volatile("bar.sync 1, 128;" ::: "memory");
            if (warp == 0 && lane < 16) {
                float a0 = 0.f, a1 = 0.f;
                #pragma unroll
                for (int q = 0; q < 4; q++) { a0 += red2[q][2 * lane]; a1 += red2[q][2 * lane + 1]; }
                int row = lane >> 1;
                int col = b * 4 + (lane & 1) * 2;
                col = (b >> 5) * 128 + (b & 31) * 4 + (lane & 1) * 2;
                st_relaxed_u64(&g_p2[b * 16 + lane], ((u64)tag << 32) | pack_bf2(a0, a1)); (void)row; (void)col;
            }
        }
        __syncthreads();
        TSTAMP(8);
    }
}

__global__ void __launch_bounds__(64) tok_attn_kernel() {
    __shared__ __align__(16) bf16 Qs[32][RS];
    __shared__ __align__(16) bf16 Ks[48][RS];
    __shared__ __align__(16) bf16 Vs[48][RS];
    const int tid = threadIdx.x, warp = tid >> 5, lane = tid & 31;
    const int g = lane >> 2, t = lane & 3;
    const int s = blockIdx.x >> 5, h = blockIdx.x & 31;
    for (int ch = tid; ch < 32 * 16; ch += 64) {
        int r = ch >> 4, cc = (ch & 15) * 8;
        const bf16* base = g_qkv + (size_t)(s * SEG_ + r) * (3 * HD_) + h * DH_ + cc;
        *reinterpret_cast<uint4*>(&Qs[r][cc]) = *reinterpret_cast<const uint4*>(base);
        *reinterpret_cast<uint4*>(&Ks[8 + r][cc]) = *reinterpret_cast<const uint4*>(base + HD_);
        *reinterpret_cast<uint4*>(&Vs[8 + r][cc]) = *reinterpret_cast<const uint4*>(base + 2 * HD_);
    }
    for (int ch = tid; ch < 8 * 16; ch += 64) {
        int r = ch >> 4, cc = (ch & 15) * 8;
        size_t off = ((size_t)s * MEM_ + r) * HD_ + h * DH_ + cc;
        *reinterpret_cast<uint4*>(&Ks[r][cc]) = *reinterpret_cast<const uint4*>(g_km + off);
        *reinterpret_cast<uint4*>(&Vs[r][cc]) = *reinterpret_cast<const uint4*>(g_vm + off);
        *reinterpret_cast<uint4*>(&Ks[40 + r][cc]) = make_uint4(0, 0, 0, 0);
        *reinterpret_cast<uint4*>(&Vs[40 + r][cc]) = make_uint4(0, 0, 0, 0);
    }
    __syncthreads();
    float sacc[5][4];
    #pragma unroll
    for (int n = 0; n < 5; n++) { sacc[n][0] = sacc[n][1] = sacc[n][2] = sacc[n][3] = 0.f; }
    #pragma unroll
    for (int kk = 0; kk < 8; kk++) {
        uint32_t a[4];
        ldmatrix_x4(a[0], a[1], a[2], a[3], smem_u32(&Qs[warp * 16 + (lane & 15)][kk * 16 + (lane >> 4) * 8]));
        #pragma unroll
        for (int n = 0; n < 5; n++) {
            uint32_t b0 = *reinterpret_cast<const uint32_t*>(&Ks[n * 8 + g][kk * 16 + 2 * t]);
            uint32_t b1 = *reinterpret_cast<const uint32_t*>(&Ks[n * 8 + g][kk * 16 + 2 * t + 8]);
            mma_bf16(sacc[n], a, b0, b1);
        }
    }
    const float scale = 0.08838834764831845f;
    float p[2][10];
    #pragma unroll
    for (int hh = 0; hh < 2; hh++) {
        int qi = 8 + warp * 16 + g + hh * 8;
        float mx = -INFINITY;
        #pragma unroll
        for (int n = 0; n < 5; n++)
            #pragma unroll
            for (int e = 0; e < 2; e++) {
                int key = n * 8 + 2 * t + e;
                float v = rbf(rbf(sacc[n][hh * 2 + e]) * scale);
                if (key > qi) v = -INFINITY;
                p[hh][n * 2 + e] = v;
                mx = fmaxf(mx, v);
            }
        mx = fmaxf(mx, __shfl_xor_sync(0xffffffffu, mx, 1));
        mx = fmaxf(mx, __shfl_xor_sync(0xffffffffu, mx, 2));
        float sum = 0.f;
        #pragma unroll
        for (int i = 0; i < 10; i++) { p[hh][i] = __expf(p[hh][i] - mx); sum += p[hh][i]; }
        sum += __shfl_xor_sync(0xffffffffu, sum, 1);
        sum += __shfl_xor_sync(0xffffffffu, sum, 2);
        float inv = 1.0f / sum;
        #pragma unroll
        for (int i = 0; i < 10; i++) p[hh][i] = rbf(p[hh][i] * inv);
    }
    #pragma unroll
    for (int dn = 0; dn < 16; dn++) {
        float o[4] = {0.f, 0.f, 0.f, 0.f};
        #pragma unroll
        for (int kk = 0; kk < 3; kk++) {
            uint32_t a[4];
            a[0] = pack_bf2(p[0][4 * kk], p[0][4 * kk + 1]);
            a[1] = pack_bf2(p[1][4 * kk], p[1][4 * kk + 1]);
            if (kk < 2) {
                a[2] = pack_bf2(p[0][4 * kk + 2], p[0][4 * kk + 3]);
                a[3] = pack_bf2(p[1][4 * kk + 2], p[1][4 * kk + 3]);
            } else { a[2] = 0u; a[3] = 0u; }
            int dcol = dn * 8 + g;
            uint32_t b0 = (uint32_t)__bfloat16_as_ushort(Vs[kk * 16 + 2 * t][dcol]) | ((uint32_t)__bfloat16_as_ushort(Vs[kk * 16 + 2 * t + 1][dcol]) << 16);
            uint32_t b1 = (uint32_t)__bfloat16_as_ushort(Vs[kk * 16 + 2 * t + 8][dcol]) | ((uint32_t)__bfloat16_as_ushort(Vs[kk * 16 + 2 * t + 9][dcol]) << 16);
            mma_bf16(o, a, b0, b1);
        }
        int row0 = s * SEG_ + warp * 16 + g;
        int col = h * DH_ + dn * 8 + 2 * t;
        *reinterpret_cast<uint32_t*>(g_ox + (size_t)row0 * HD_ + col) = pack_bf2(o[0], o[1]);
        *reinterpret_cast<uint32_t*>(g_ox + (size_t)(row0 + 8) * HD_ + col) = pack_bf2(o[2], o[3]);
    }
}

extern "C" void kernel_launch(void* const* d_in, const int* in_sizes, int n_in,
                              void* d_out, int out_size) {
    const bf16* A_x = (const bf16*)d_in[0];
    const bf16* A_mem0 = (const bf16*)d_in[1];
    const bf16* A_Wq = (const bf16*)d_in[2];
    const bf16* A_Wk = (const bf16*)d_in[3];
    const bf16* A_Wv = (const bf16*)d_in[4];
    const bf16* A_Wo = (const bf16*)d_in[5];
    const bf16* B_w1 = (const bf16*)d_in[8];
    const bf16* B_w2 = (const bf16*)d_in[9];
    const bf16* B_w3 = (const bf16*)d_in[10];
    const bf16* B_w4 = (const bf16*)d_in[11];
    const bf16* c = (const bf16*)d_in[12];
    const bf16* w_mod = (const bf16*)d_in[13];
    bf16* out = (bf16*)d_out;

    const int gemm_smem = (3 * GBM * GAS + 3 * GBK * GBS) * 2;
    cudaFuncSetAttribute(gemm_kernel<0>, cudaFuncAttributeMaxDynamicSharedMemorySize, gemm_smem);
    cudaFuncSetAttribute(gemm_kernel<1>, cudaFuncAttributeMaxDynamicSharedMemorySize, gemm_smem);
    cudaFuncSetAttribute(gemm_kernel<2>, cudaFuncAttributeMaxDynamicSharedMemorySize, gemm_smem);
    cudaFuncSetAttribute(gemm_kernel<3>, cudaFuncAttributeMaxDynamicSharedMemorySize, gemm_smem);

    bf16 *p_h, *p_qkv, *p_ox, *p_hn, *p_g1, *p_x1b, *p_hn2, *p_g2, *p_hb, *p_x1;
    cudaGetSymbolAddress((void**)&p_h, g_h);
    cudaGetSymbolAddress((void**)&p_qkv, g_qkv);
    cudaGetSymbolAddress((void**)&p_ox, g_ox);
    cudaGetSymbolAddress((void**)&p_hn, g_hn);
    cudaGetSymbolAddress((void**)&p_g1, g_g1);
    cudaGetSymbolAddress((void**)&p_x1b, g_x1b);
    cudaGetSymbolAddress((void**)&p_hn2, g_hn2);
    cudaGetSymbolAddress((void**)&p_g2, g_g2);
    cudaGetSymbolAddress((void**)&p_hb, g_hb);
    cudaGetSymbolAddress((void**)&p_x1, g_x1);

    mod_kernel<<<48, 256>>>(c, w_mod);
    ln_mod_kernel<<<S_ / 8, 256>>>(A_x, p_h, 0, D_);

    static EncFn enc = nullptr;
    if (!enc) { void* fp = nullptr; cudaDriverEntryPointQueryResult qr; cudaGetDriverEntryPoint("cuTensorMapEncodeTiled", &fp, cudaEnableDefault, &qr); enc = (EncFn)fp; }
    cudaFuncSetAttribute(wg_gemm<0>, cudaFuncAttributeMaxDynamicSharedMemorySize, WG_SMEM);
    cudaFuncSetAttribute(wg_gemm<1>, cudaFuncAttributeMaxDynamicSharedMemorySize, WG_SMEM);
    cudaFuncSetAttribute(wg_gemm<2>, cudaFuncAttributeMaxDynamicSharedMemorySize, WG_SMEM);
    cudaFuncSetAttribute(wg_gemm<3>, cudaFuncAttributeMaxDynamicSharedMemorySize, WG_SMEM);
    cudaFuncSetAttribute(wg_gemm<4>, cudaFuncAttributeMaxDynamicSharedMemorySize, WG_SMEM);
    float* p_part; cudaGetSymbolAddress((void**)&p_part, g_part);
    WgParams p{};
    {
        CUtensorMap a = make_map(enc, p_h, D_, S_, 64, 128), b0 = make_map(enc, A_Wq, HD_, D_, 64, 64), b1 = make_map(enc, A_Wk, HD_, D_, 64, 64), b2 = make_map(enc, A_Wv, HD_, D_, 64, 64);
        p.M = S_; p.N = 3 * HD_; p.K = D_; p.ldc = 3 * HD_; p.nsplit = HD_; p.shifted = 0; p.ksplit_len = D_; p.out = p_qkv;
        wg_gemm<0><<<dim3(3 * HD_ / 128, S_ / 128, 1), 288, WG_SMEM>>>(a, b0, b1, b2, p);
    }
    cudaFuncSetAttribute(recur_kernel, cudaFuncAttributeMaxDynamicSharedMemorySize, 56 * 1024);
    recur_kernel<<<128, 512, 56 * 1024>>>(A_mem0, A_Wq, A_Wk, A_Wv, A_Wo);
    tok_attn_kernel<<<NSEG_ * H_, 64>>>();
    {
        CUtensorMap a = make_map(enc, p_ox, HD_, S_, 64, 128), b = make_map(enc, A_Wo, D_, HD_, 64, 64);
        p.M = S_; p.N = D_; p.K = HD_; p.ldc = D_; p.nsplit = D_; p.ksplit_len = HD_ / 2; p.outf = p_part;
        wg_gemm<4><<<dim3(4, 16, 2), 288, WG_SMEM>>>(a, b, b, b, p);
    }
    res_ln2_kernel<<<S_ / 8, 256>>>(A_x);
    {
        CUtensorMap a = make_map(enc, p_hn, D_, S_, 64, 128), b = make_map(enc, B_w1, D_, D_, 64, 64);
        p.K = D_; p.ksplit_len = D_; p.out = p_g1;
        wg_gemm<1><<<dim3(4, 16, 1), 288, WG_SMEM>>>(a, b, b, b, p);
    }
    {
        CUtensorMap a = make_map(enc, p_g1, D_, S_, 64, 128), b = make_map(enc, B_w2, D_, D_, 64, 64);
        p.out = p_x1b; p.res = p_hb; p.shifted = 1;
        wg_gemm<2><<<dim3(4, 16, 1), 288, WG_SMEM>>>(a, b, b, b, p);
        p.shifted = 0;
    }
    ln_kernel<<<S_ / 8, 256>>>(p_x1b, p_hn2);
    {
        CUtensorMap a = make_map(enc, p_hn2, D_, S_, 64, 128), b = make_map(enc, B_w3, F_, D_, 64, 64);
        p.N = F_; p.ldc = F_; p.nsplit = F_; p.out = p_g2;
        wg_gemm<1><<<dim3(11, 16, 1), 288, WG_SMEM>>>(a, b, b, b, p);
    }
    {
        CUtensorMap a = make_map(enc, p_g2, F_, S_, 64, 128), b = make_map(enc, B_w4, D_, F_, 64, 64);
        p.N = D_; p.K = F_; p.ksplit_len = F_; p.ldc = D_; p.nsplit = D_; p.out = out; p.res = p_x1b; p.res2 = p_x1;
        wg_gemm<3><<<dim3(4, 16, 1), 288, WG_SMEM>>>(a, b, b, b, p);
    }
}
```
